```python
import torch

def _softmax(x, axis=-1):
    return torch.softmax(x, dim=axis)
def _gelu(x):
    return torch.nn.functional.gelu(x, approximate="tanh")
def _silu(x):
    return torch.nn.functional.silu(x)
def _sigmoid(x):
    return torch.sigmoid(x)
def _layernorm(x, axis=-1, eps=1e-5):
    m = x.mean(dim=axis, keepdim=True)
    v = x.var(dim=axis, keepdim=True, unbiased=False)
    return (x - m) / torch.sqrt(v + eps)
def _scatter_add(tgt, idx, src, axis=0):
    return tgt.clone().index_add_(axis, idx, src)
def _segment_sum(src, seg, n):
    out = torch.zeros((n,) + src.shape[1:], dtype=src.dtype)
    return out.index_add_(0, seg, src)
def _pad(x, pw):
    flat = tuple(v for pair in reversed(pw) for v in pair)
    return torch.nn.functional.pad(x, flat)

kernel_name = 'interleave_layers__linear_attn_block__dense_activation_gelu__prompt'

def setup_inputs():

    _w = (lambda a: (lambda t: t.to(torch.bfloat16) if t.is_floating_point() else t)(torch.as_tensor(a)))
    def _A_setup():
        B, S, D = 1, 2048, 512
        return {
            "x": _w((lambda *s: torch.randn(*s, dtype=torch.bfloat16) * 0.05)(B, S, D)),
            "wqkv": _w((lambda *s: torch.randn(*s, dtype=torch.bfloat16) * 0.05)(D, 3 * D)),
            "wo": _w((lambda *s: torch.randn(*s, dtype=torch.bfloat16) * 0.05)(D, D)),
        }
    _A_in = _A_setup()

    def _B_setup():
        B, S, D, F = 1, 2048, 512, 1792
        return {
            "x": _w((lambda *s: torch.randn(*s, dtype=torch.bfloat16) * 0.05)(B, S, D)),
            "w1": _w((lambda *s: torch.randn(*s, dtype=torch.bfloat16) * 0.8)(D, F) * (D ** -0.5)),
            "b1": _w((lambda *s: torch.randn(*s, dtype=torch.bfloat16) * 0.8)(F) * 0.01),
            "w2": _w((lambda *s: torch.randn(*s, dtype=torch.bfloat16) * 0.8)(F, D) * (F ** -0.5)),
            "b2": _w((lambda *s: torch.randn(*s, dtype=torch.bfloat16) * 0.8)(D) * 0.01),
        }
    _B_in = _B_setup()

    return {
        "A_x": _A_in["x"],
        "A_wqkv": _A_in["wqkv"],
        "A_wo": _A_in["wo"],
        "B_x": _B_in["x"],
        "B_w1": _B_in["w1"],
        "B_b1": _B_in["b1"],
        "B_w2": _B_in["w2"],
        "B_b2": _B_in["b2"],
    }

def reference(A_x, A_wqkv, A_wo, B_x, B_w1, B_b1, B_w2, B_b2):
    def _A_ref(x, wqkv, wo):
        B, S, D = x.shape
        H = 32; Dh = D // H
        qkv = (lambda x, *d: x.permute(*d))((x @ wqkv).reshape(B, S, 3, H, Dh), 2, 0, 3, 1, 4)
        q, k, v = qkv[0], qkv[1], qkv[2]
        phi = lambda t: torch.where(t > 0, t + 1, torch.exp(t)) + 1e-6
        pq, pk = phi(q), phi(k)
        kv = torch.einsum("bhsd,bhse->bhde", pk, v)
        z = torch.einsum("bhsd->bhd", pk)
        num = torch.einsum("bhqd,bhde->bhqe", pq, kv)
        den = torch.einsum("bhqd,bhd->bhq", pq, z)[..., None] + 1e-6
        o = num / den
        return (lambda x, *d: x.permute(*d))(o, 0, 2, 1, 3).reshape(B, S, D) @ wo

    def _B_ref(x, w1, b1, w2, b2):
        h = torch.einsum("bsd,df->bsf", x, w1) + b1
        h = _gelu(h)
        return torch.einsum("bsf,fd->bsd", h, w2) + b2

    x = A_x
    x = x + _A_ref(_layernorm(x, axis=-1), A_wqkv, A_wo)
    x = x + _B_ref(_layernorm(x, axis=-1), B_w1, B_b1, B_w2, B_b2)
    x = x + _A_ref(_layernorm(x, axis=-1), A_wqkv, A_wo)
    x = x + _B_ref(_layernorm(x, axis=-1), B_w1, B_b1, B_w2, B_b2)
    return x
```

```cpp
#include <cuda_runtime.h>
#include <cuda_bf16.h>
#include <cuda.h>
#include <stdint.h>
#define KB(i) ((i) ? (i) - ((i) <= c) : c)
#define HS(k) (2 * ((k) ? (k) - ((k) <= (c >> 1)) : c >> 1) + (c & 1))

namespace {

constexpr int D_ = 512;
constexpr int FS = 224;
constexpr uint32_t SB = 1024;
constexpr int SLOT = 28672;
constexpr uint32_t FULL = SB + 8 * SLOT, EMPTY = FULL + 64, KVBAR = FULL + 128, CSBAR = FULL + 136, CPBAR = FULL + 144, XBAR = FULL + 152, W1BAR = FULL + 216;
constexpr uint32_t SM_CQ = FULL + 224;
constexpr uint32_t SM_B1 = SM_CQ + 768;
constexpr uint32_t SM_B2 = SM_B1 + FS * 8;
constexpr int SMEM_BYTES = SM_B2 + 256 - SB;
constexpr uint32_t P_STG = SB + 4 * SLOT + 16384;
constexpr uint32_t P_ONES = P_STG + 8192, P_KVF = P_ONES + 1024, P_ZF = P_KVF + 2048, P_CS = SM_B1;
__device__ __forceinline__ uint32_t xunit(int u) { return SB + 4096 * (u < 14 ? 42 + u : u - 10 + ((u - 14) * 11 >> 5) * 4); }

struct Xrg {
    uint4 x[2][2][8][4][128];
    uint4 o[2][8][4][128];
    uint4 h[2][8][14][128];
    uint4 p[2][8][4][128];
    uint4 st[2][2][4][8][8];
};
struct Xchg {
    uint4 kvp[8][16][144];
    uint4 cs[2][8][128];
    Xrg r[16];
};
__device__ __align__(1024) Xchg g_xchg;

__device__ __forceinline__ void mbar_init(uint32_t bar, uint32_t cnt) { asm volatile("mbarrier.init.shared::cta.b64 [%0], %1;" ::"r"(bar), "r"(cnt) : "memory"); }
__device__ __forceinline__ void mbar_arrive(uint32_t bar) { asm volatile("mbarrier.arrive.shared::cta.b64 _, [%0];" ::"r"(bar) : "memory"); }
constexpr int SPIN_MAX = 1 << 14;
__device__ __forceinline__ void mbar_wait(uint32_t bar, uint32_t parity) {
    asm volatile("{ .reg .pred p; .reg .u32 n; mov.u32 n, 0;\n"
                 "W%=: mbarrier.try_wait.parity.shared::cta.b64 p, [%0], %1; @p bra D%=;\n"
                 "add.u32 n, n, 1; setp.lt.u32 p, n, 16384; @p bra W%=;\n"
                 "D%=: }" ::"r"(bar), "r"(parity) : "memory");
}
__device__ __forceinline__ void mbar_wait2(uint32_t bar, uint32_t parity) {
    asm volatile("{ .reg .pred p, q; .reg .u32 n; mov.u32 n, 0;\n"
                 "W%=: mbarrier.try_wait.parity.shared::cta.b64 p, [%0], %1; mbarrier.try_wait.parity.shared::cta.b64 q, [%0+8], %1; and.pred p, p, q; @p bra D%=;\n"
                 "add.u32 n, n, 1; setp.lt.u32 p, n, 16384; @p bra W%=;\n"
                 "D%=: }" ::"r"(bar), "r"(parity) : "memory");
}
#define LD128(A, B, C, D, P) "ld.relaxed.gpu.global.b128 t, [" P "]; mov.b128 {l, h}, t; mov.b64 {" A "," B "}, l; mov.b64 {" C "," D "}, h;\n"
__device__ __forceinline__ uint4 ld_ll(const uint4* p) {
    uint4 v;
    asm volatile("{ .reg .b128 t; .reg .b64 l, h; " LD128("%0", "%1", "%2", "%3", "%4") "}" : "=r"(v.x), "=r"(v.y), "=r"(v.z), "=r"(v.w) : "l"(p) : "memory");
    return v;
}
__device__ __forceinline__ void st_ll(uint4* p, uint32_t a, uint32_t b, uint32_t c, uint32_t d) {
    asm volatile("{ .reg .b128 t; .reg .b64 l, h; mov.b64 l, {%1,%2}; mov.b64 h, {%3,%4}; mov.b128 t, {l, h}; st.relaxed.gpu.global.b128 [%0], t; }"
                 ::"l"(p), "r"(a), "r"(b), "r"(c), "r"(d) : "memory");
}
__device__ __forceinline__ void st_ll1(uint32_t* p, uint32_t a) { asm volatile("st.relaxed.gpu.global.u32 [%0], %1;" ::"l"(p), "r"(a) : "memory"); }
__device__ __forceinline__ uint32_t tg(uint32_t w, uint32_t tag) { return (w & ~1u) | tag; }
__device__ __forceinline__ uint32_t fu(float f) { return __float_as_uint(f); }
__device__ __forceinline__ float uf(uint32_t u) { return __uint_as_float(u); }
__device__ __forceinline__ uint32_t pack2(float lo, float hi) {
    uint32_t r; asm("cvt.rn.bf16x2.f32 %0, %1, %2;" : "=r"(r) : "f"(hi), "f"(lo)); return r;
}
__device__ __forceinline__ float lo_f(uint32_t w) { return uf(w << 16); }
__device__ __forceinline__ float hi_f(uint32_t w) { return uf(w & 0xffff0000u); }
__device__ __forceinline__ float phi(float a, float r, float re) {
    float e; asm("ex2.approx.ftz.f32 %0, %1;" : "=f"(e) : "f"(a * re));
    return (a > 0.f ? fmaf(a, r, 1.f) : e) + 1e-6f;
}
__device__ __forceinline__ float gelu2(float hh) {
    float u = hh * fmaf(hh * hh, 8.f * 0.044715f * 0.7978845608028654f, 2.f * 0.7978845608028654f), th;
    asm("tanh.approx.f32 %0, %1;" : "=f"(th) : "f"(u));
    return fmaf(hh, th, hh);
}
__device__ __forceinline__ float rcp(float x) { float r; asm("rcp.approx.ftz.f32 %0, %1;" : "=f"(r) : "f"(x)); return r; }
__device__ __forceinline__ void wg_fence() { asm volatile("wgmma.fence.sync.aligned;" ::: "memory"); }
__device__ __forceinline__ void wg_commit() { asm volatile("wgmma.commit_group.sync.aligned;" ::: "memory"); }
template <int N> __device__ __forceinline__ void wg_wait() { asm volatile("wgmma.wait_group.sync.aligned %0;" ::"n"(N) : "memory"); }
template <int N> __device__ __forceinline__ void keep(float (&d)[N]) {
#pragma unroll
    for (int i = 0; i < N; i++) asm volatile("" : "+f"(d[i])::"memory");
}
__device__ __forceinline__ constexpr uint64_t mkdesc(uint32_t addr, uint32_t lbo, uint32_t sbo, uint32_t swz) {
    return (uint64_t)(addr >> 4) | ((uint64_t)(lbo >> 4) << 16) | ((uint64_t)(sbo >> 4) << 32) | ((uint64_t)swz << 62);
}
__device__ __forceinline__ void mma16816(float (&c)[4], const uint32_t* a, uint32_t b0, uint32_t b1) {
    asm volatile("mma.sync.aligned.m16n8k16.row.col.f32.bf16.bf16.f32 {%0,%1,%2,%3}, {%4,%5,%6,%7}, {%8,%9}, {%10,%10,%10,%10};"
                 : "=f"(c[0]), "=f"(c[1]), "=f"(c[2]), "=f"(c[3]) : "r"(a[0]), "r"(a[1]), "r"(a[2]), "r"(a[3]), "r"(b0), "r"(b1), "f"(0.f));
}
__device__ __forceinline__ void colsum16(float (&c)[4], uint32_t u, uint32_t v) {
    asm volatile("{ .reg .b32 b0, b1; movmatrix.sync.aligned.m8n8.trans.b16 b0, %4; movmatrix.sync.aligned.m8n8.trans.b16 b1, %5;\n"
                 "mma.sync.aligned.m16n8k16.row.col.f32.bf16.bf16.f32 {%0,%1,%2,%3}, {%6,%6,%6,%6}, {b0,b1}, {%0,%1,%2,%3}; }"
                 : "+f"(c[0]), "+f"(c[1]), "+f"(c[2]), "+f"(c[3]) : "r"(u), "r"(v), "r"(0x3f803f80u));
}
__device__ __forceinline__ void stsm4(uint32_t addr, uint32_t a, uint32_t b, uint32_t c, uint32_t d) {
    asm volatile("stmatrix.sync.aligned.m8n8.x4.shared.b16 [%0], {%1,%2,%3,%4};" ::"r"(addr), "r"(a), "r"(b), "r"(c), "r"(d) : "memory");
}
__device__ __forceinline__ float2 lds2(uint32_t a) { float2 v; asm volatile("ld.shared.v2.f32 {%0,%1}, [%2];" : "=f"(v.x), "=f"(v.y) : "r"(a)); return v; }
__device__ __forceinline__ float4 lds4(uint32_t a) { float4 v; asm volatile("ld.shared.v4.f32 {%0,%1,%2,%3}, [%4];" : "=f"(v.x), "=f"(v.y), "=f"(v.z), "=f"(v.w) : "r"(a)); return v; }
__device__ __forceinline__ void sts2(uint32_t a, float u, float v) { asm volatile("st.shared.v2.f32 [%0], {%1,%2};" ::"r"(a), "f"(u), "f"(v) : "memory"); }
__device__ __forceinline__ void ldsm4(uint32_t* a, uint32_t addr) {
    asm volatile("ldmatrix.sync.aligned.m8n8.x4.shared.b16 {%0,%1,%2,%3}, [%4];" : "=r"(a[0]), "=r"(a[1]), "=r"(a[2]), "=r"(a[3]) : "r"(addr) : "memory");
}
__device__ __forceinline__ void acc_bf(float* c, uint32_t u, uint32_t v, uint32_t id) {
    asm volatile("mma.sync.aligned.m16n8k8.row.col.f32.bf16.bf16.f32 {%0,%1,%2,%3}, {%4,%5}, {%6}, {%0,%1,%2,%3};"
                 : "+f"(c[0]), "+f"(c[1]), "+f"(c[2]), "+f"(c[3]) : "r"(u), "r"(v), "r"(id));
}
__device__ __forceinline__ uint32_t nae(uint32_t a, uint32_t b, uint32_t t) { uint32_t r; asm("lop3.b32 %0, %1, %2, %3, 0x7e;" : "=r"(r) : "r"(a), "r"(b), "r"(t)); return r; }
__device__ __forceinline__ void l2_prefetch(const void* p, uint32_t bytes) {
    asm volatile("cp.async.bulk.prefetch.L2.global [%0], %1;" ::"l"(p), "r"(bytes) : "memory");
}
__device__ __forceinline__ void release(uint32_t eb, uint32_t slot, bool on) {
    if (on) asm volatile("mbarrier.arrive.shared::cluster.b64 _, [%0];" ::"r"(eb + slot * 8) : "memory");
}

__device__ __forceinline__ void pair_wait() { asm volatile("barrier.cluster.wait.aligned;" ::: "memory"); }

__device__ __forceinline__ void wgmma_rs_n128(float (&d)[64], const uint32_t* a, uint64_t db) {
    asm volatile("wgmma.mma_async.sync.aligned.m64n128k16.f32.bf16.bf16 {%0, %1, %2, %3, %4, %5, %6, %7, %8, %9, %10, %11, %12, %13, %14, %15, %16, %17, %18, %19, %20, %21, %22, %23, %24, %25, %26, %27, %28, %29, %30, %31, %32, %33, %34, %35, %36, %37, %38, %39, %40, %41, %42, %43, %44, %45, %46, %47, %48, %49, %50, %51, %52, %53, %54, %55, %56, %57, %58, %59, %60, %61, %62, %63}, {%64, %65, %66, %67}, %68, 1, 1, 1, 1;"
        : "+f"(d[0]), "+f"(d[1]), "+f"(d[2]), "+f"(d[3]), "+f"(d[4]), "+f"(d[5]), "+f"(d[6]), "+f"(d[7]), "+f"(d[8]), "+f"(d[9]), "+f"(d[10]), "+f"(d[11]), "+f"(d[12]), "+f"(d[13]), "+f"(d[14]), "+f"(d[15]), "+f"(d[16]), "+f"(d[17]), "+f"(d[18]), "+f"(d[19]), "+f"(d[20]), "+f"(d[21]), "+f"(d[22]), "+f"(d[23]), "+f"(d[24]), "+f"(d[25]), "+f"(d[26]), "+f"(d[27]), "+f"(d[28]), "+f"(d[29]), "+f"(d[30]), "+f"(d[31]), "+f"(d[32]), "+f"(d[33]), "+f"(d[34]), "+f"(d[35]), "+f"(d[36]), "+f"(d[37]), "+f"(d[38]), "+f"(d[39]), "+f"(d[40]), "+f"(d[41]), "+f"(d[42]), "+f"(d[43]), "+f"(d[44]), "+f"(d[45]), "+f"(d[46]), "+f"(d[47]), "+f"(d[48]), "+f"(d[49]), "+f"(d[50]), "+f"(d[51]), "+f"(d[52]), "+f"(d[53]), "+f"(d[54]), "+f"(d[55]), "+f"(d[56]), "+f"(d[57]), "+f"(d[58]), "+f"(d[59]), "+f"(d[60]), "+f"(d[61]), "+f"(d[62]), "+f"(d[63])
        : "r"(a[0]), "r"(a[1]), "r"(a[2]), "r"(a[3]), "l"(db));
}

__device__ __forceinline__ void wgmma_rs_n224(float (&d)[112], const uint32_t* a, uint64_t db) {
    asm volatile("wgmma.mma_async.sync.aligned.m64n224k16.f32.bf16.bf16 {%0, %1, %2, %3, %4, %5, %6, %7, %8, %9, %10, %11, %12, %13, %14, %15, %16, %17, %18, %19, %20, %21, %22, %23, %24, %25, %26, %27, %28, %29, %30, %31, %32, %33, %34, %35, %36, %37, %38, %39, %40, %41, %42, %43, %44, %45, %46, %47, %48, %49, %50, %51, %52, %53, %54, %55, %56, %57, %58, %59, %60, %61, %62, %63, %64, %65, %66, %67, %68, %69, %70, %71, %72, %73, %74, %75, %76, %77, %78, %79, %80, %81, %82, %83, %84, %85, %86, %87, %88, %89, %90, %91, %92, %93, %94, %95, %96, %97, %98, %99, %100, %101, %102, %103, %104, %105, %106, %107, %108, %109, %110, %111}, {%112, %113, %114, %115}, %116, 1, 1, 1, 1;"
        : "+f"(d[0]), "+f"(d[1]), "+f"(d[2]), "+f"(d[3]), "+f"(d[4]), "+f"(d[5]), "+f"(d[6]), "+f"(d[7]), "+f"(d[8]), "+f"(d[9]), "+f"(d[10]), "+f"(d[11]), "+f"(d[12]), "+f"(d[13]), "+f"(d[14]), "+f"(d[15]), "+f"(d[16]), "+f"(d[17]), "+f"(d[18]), "+f"(d[19]), "+f"(d[20]), "+f"(d[21]), "+f"(d[22]), "+f"(d[23]), "+f"(d[24]), "+f"(d[25]), "+f"(d[26]), "+f"(d[27]), "+f"(d[28]), "+f"(d[29]), "+f"(d[30]), "+f"(d[31]), "+f"(d[32]), "+f"(d[33]), "+f"(d[34]), "+f"(d[35]), "+f"(d[36]), "+f"(d[37]), "+f"(d[38]), "+f"(d[39]), "+f"(d[40]), "+f"(d[41]), "+f"(d[42]), "+f"(d[43]), "+f"(d[44]), "+f"(d[45]), "+f"(d[46]), "+f"(d[47]), "+f"(d[48]), "+f"(d[49]), "+f"(d[50]), "+f"(d[51]), "+f"(d[52]), "+f"(d[53]), "+f"(d[54]), "+f"(d[55]), "+f"(d[56]), "+f"(d[57]), "+f"(d[58]), "+f"(d[59]), "+f"(d[60]), "+f"(d[61]), "+f"(d[62]), "+f"(d[63]), "+f"(d[64]), "+f"(d[65]), "+f"(d[66]), "+f"(d[67]), "+f"(d[68]), "+f"(d[69]), "+f"(d[70]), "+f"(d[71]), "+f"(d[72]), "+f"(d[73]), "+f"(d[74]), "+f"(d[75]), "+f"(d[76]), "+f"(d[77]), "+f"(d[78]), "+f"(d[79]), "+f"(d[80]), "+f"(d[81]), "+f"(d[82]), "+f"(d[83]), "+f"(d[84]), "+f"(d[85]), "+f"(d[86]), "+f"(d[87]), "+f"(d[88]), "+f"(d[89]), "+f"(d[90]), "+f"(d[91]), "+f"(d[92]), "+f"(d[93]), "+f"(d[94]), "+f"(d[95]), "+f"(d[96]), "+f"(d[97]), "+f"(d[98]), "+f"(d[99]), "+f"(d[100]), "+f"(d[101]), "+f"(d[102]), "+f"(d[103]), "+f"(d[104]), "+f"(d[105]), "+f"(d[106]), "+f"(d[107]), "+f"(d[108]), "+f"(d[109]), "+f"(d[110]), "+f"(d[111])
        : "r"(a[0]), "r"(a[1]), "r"(a[2]), "r"(a[3]), "l"(db));
}

__device__ __forceinline__ void wgmma_rs_n64(float (&d)[32], const uint32_t* a, uint64_t db) {
    asm volatile("wgmma.mma_async.sync.aligned.m64n64k16.f32.bf16.bf16 {%0, %1, %2, %3, %4, %5, %6, %7, %8, %9, %10, %11, %12, %13, %14, %15, %16, %17, %18, %19, %20, %21, %22, %23, %24, %25, %26, %27, %28, %29, %30, %31}, {%32, %33, %34, %35}, %36, 1, 1, 1, 1;"
        : "+f"(d[0]), "+f"(d[1]), "+f"(d[2]), "+f"(d[3]), "+f"(d[4]), "+f"(d[5]), "+f"(d[6]), "+f"(d[7]), "+f"(d[8]), "+f"(d[9]), "+f"(d[10]), "+f"(d[11]), "+f"(d[12]), "+f"(d[13]), "+f"(d[14]), "+f"(d[15]), "+f"(d[16]), "+f"(d[17]), "+f"(d[18]), "+f"(d[19]), "+f"(d[20]), "+f"(d[21]), "+f"(d[22]), "+f"(d[23]), "+f"(d[24]), "+f"(d[25]), "+f"(d[26]), "+f"(d[27]), "+f"(d[28]), "+f"(d[29]), "+f"(d[30]), "+f"(d[31])
        : "r"(a[0]), "r"(a[1]), "r"(a[2]), "r"(a[3]), "l"(db));
}

__device__ __forceinline__ void wgmma_rsz_n128(float (&d)[64], const uint32_t* a, uint64_t db) {
    asm volatile("wgmma.mma_async.sync.aligned.m64n128k16.f32.bf16.bf16 {%0, %1, %2, %3, %4, %5, %6, %7, %8, %9, %10, %11, %12, %13, %14, %15, %16, %17, %18, %19, %20, %21, %22, %23, %24, %25, %26, %27, %28, %29, %30, %31, %32, %33, %34, %35, %36, %37, %38, %39, %40, %41, %42, %43, %44, %45, %46, %47, %48, %49, %50, %51, %52, %53, %54, %55, %56, %57, %58, %59, %60, %61, %62, %63}, {%64, %65, %66, %67}, %68, 0, 1, 1, 1;"
        : "=f"(d[0]), "=f"(d[1]), "=f"(d[2]), "=f"(d[3]), "=f"(d[4]), "=f"(d[5]), "=f"(d[6]), "=f"(d[7]), "=f"(d[8]), "=f"(d[9]), "=f"(d[10]), "=f"(d[11]), "=f"(d[12]), "=f"(d[13]), "=f"(d[14]), "=f"(d[15]), "=f"(d[16]), "=f"(d[17]), "=f"(d[18]), "=f"(d[19]), "=f"(d[20]), "=f"(d[21]), "=f"(d[22]), "=f"(d[23]), "=f"(d[24]), "=f"(d[25]), "=f"(d[26]), "=f"(d[27]), "=f"(d[28]), "=f"(d[29]), "=f"(d[30]), "=f"(d[31]), "=f"(d[32]), "=f"(d[33]), "=f"(d[34]), "=f"(d[35]), "=f"(d[36]), "=f"(d[37]), "=f"(d[38]), "=f"(d[39]), "=f"(d[40]), "=f"(d[41]), "=f"(d[42]), "=f"(d[43]), "=f"(d[44]), "=f"(d[45]), "=f"(d[46]), "=f"(d[47]), "=f"(d[48]), "=f"(d[49]), "=f"(d[50]), "=f"(d[51]), "=f"(d[52]), "=f"(d[53]), "=f"(d[54]), "=f"(d[55]), "=f"(d[56]), "=f"(d[57]), "=f"(d[58]), "=f"(d[59]), "=f"(d[60]), "=f"(d[61]), "=f"(d[62]), "=f"(d[63])
        : "r"(a[0]), "r"(a[1]), "r"(a[2]), "r"(a[3]), "l"(db));
}

__device__ __forceinline__ void wgmma_rsz_n224(float (&d)[112], const uint32_t* a, uint64_t db) {
    asm volatile("wgmma.mma_async.sync.aligned.m64n224k16.f32.bf16.bf16 {%0, %1, %2, %3, %4, %5, %6, %7, %8, %9, %10, %11, %12, %13, %14, %15, %16, %17, %18, %19, %20, %21, %22, %23, %24, %25, %26, %27, %28, %29, %30, %31, %32, %33, %34, %35, %36, %37, %38, %39, %40, %41, %42, %43, %44, %45, %46, %47, %48, %49, %50, %51, %52, %53, %54, %55, %56, %57, %58, %59, %60, %61, %62, %63, %64, %65, %66, %67, %68, %69, %70, %71, %72, %73, %74, %75, %76, %77, %78, %79, %80, %81, %82, %83, %84, %85, %86, %87, %88, %89, %90, %91, %92, %93, %94, %95, %96, %97, %98, %99, %100, %101, %102, %103, %104, %105, %106, %107, %108, %109, %110, %111}, {%112, %113, %114, %115}, %116, 0, 1, 1, 1;"
        : "=f"(d[0]), "=f"(d[1]), "=f"(d[2]), "=f"(d[3]), "=f"(d[4]), "=f"(d[5]), "=f"(d[6]), "=f"(d[7]), "=f"(d[8]), "=f"(d[9]), "=f"(d[10]), "=f"(d[11]), "=f"(d[12]), "=f"(d[13]), "=f"(d[14]), "=f"(d[15]), "=f"(d[16]), "=f"(d[17]), "=f"(d[18]), "=f"(d[19]), "=f"(d[20]), "=f"(d[21]), "=f"(d[22]), "=f"(d[23]), "=f"(d[24]), "=f"(d[25]), "=f"(d[26]), "=f"(d[27]), "=f"(d[28]), "=f"(d[29]), "=f"(d[30]), "=f"(d[31]), "=f"(d[32]), "=f"(d[33]), "=f"(d[34]), "=f"(d[35]), "=f"(d[36]), "=f"(d[37]), "=f"(d[38]), "=f"(d[39]), "=f"(d[40]), "=f"(d[41]), "=f"(d[42]), "=f"(d[43]), "=f"(d[44]), "=f"(d[45]), "=f"(d[46]), "=f"(d[47]), "=f"(d[48]), "=f"(d[49]), "=f"(d[50]), "=f"(d[51]), "=f"(d[52]), "=f"(d[53]), "=f"(d[54]), "=f"(d[55]), "=f"(d[56]), "=f"(d[57]), "=f"(d[58]), "=f"(d[59]), "=f"(d[60]), "=f"(d[61]), "=f"(d[62]), "=f"(d[63]), "=f"(d[64]), "=f"(d[65]), "=f"(d[66]), "=f"(d[67]), "=f"(d[68]), "=f"(d[69]), "=f"(d[70]), "=f"(d[71]), "=f"(d[72]), "=f"(d[73]), "=f"(d[74]), "=f"(d[75]), "=f"(d[76]), "=f"(d[77]), "=f"(d[78]), "=f"(d[79]), "=f"(d[80]), "=f"(d[81]), "=f"(d[82]), "=f"(d[83]), "=f"(d[84]), "=f"(d[85]), "=f"(d[86]), "=f"(d[87]), "=f"(d[88]), "=f"(d[89]), "=f"(d[90]), "=f"(d[91]), "=f"(d[92]), "=f"(d[93]), "=f"(d[94]), "=f"(d[95]), "=f"(d[96]), "=f"(d[97]), "=f"(d[98]), "=f"(d[99]), "=f"(d[100]), "=f"(d[101]), "=f"(d[102]), "=f"(d[103]), "=f"(d[104]), "=f"(d[105]), "=f"(d[106]), "=f"(d[107]), "=f"(d[108]), "=f"(d[109]), "=f"(d[110]), "=f"(d[111])
        : "r"(a[0]), "r"(a[1]), "r"(a[2]), "r"(a[3]), "l"(db));
}

__device__ __forceinline__ void wgmma_rsz_n64(float (&d)[32], const uint32_t* a, uint64_t db) {
    asm volatile("wgmma.mma_async.sync.aligned.m64n64k16.f32.bf16.bf16 {%0, %1, %2, %3, %4, %5, %6, %7, %8, %9, %10, %11, %12, %13, %14, %15, %16, %17, %18, %19, %20, %21, %22, %23, %24, %25, %26, %27, %28, %29, %30, %31}, {%32, %33, %34, %35}, %36, 0, 1, 1, 1;"
        : "=f"(d[0]), "=f"(d[1]), "=f"(d[2]), "=f"(d[3]), "=f"(d[4]), "=f"(d[5]), "=f"(d[6]), "=f"(d[7]), "=f"(d[8]), "=f"(d[9]), "=f"(d[10]), "=f"(d[11]), "=f"(d[12]), "=f"(d[13]), "=f"(d[14]), "=f"(d[15]), "=f"(d[16]), "=f"(d[17]), "=f"(d[18]), "=f"(d[19]), "=f"(d[20]), "=f"(d[21]), "=f"(d[22]), "=f"(d[23]), "=f"(d[24]), "=f"(d[25]), "=f"(d[26]), "=f"(d[27]), "=f"(d[28]), "=f"(d[29]), "=f"(d[30]), "=f"(d[31])
        : "r"(a[0]), "r"(a[1]), "r"(a[2]), "r"(a[3]), "l"(db));
}

template <int TA, int TB> __device__ __forceinline__ void wgmma_ss_n64(float (&d)[32], uint64_t da, uint64_t db) {
    asm volatile("wgmma.mma_async.sync.aligned.m64n64k16.f32.bf16.bf16 {%0, %1, %2, %3, %4, %5, %6, %7, %8, %9, %10, %11, %12, %13, %14, %15, %16, %17, %18, %19, %20, %21, %22, %23, %24, %25, %26, %27, %28, %29, %30, %31}, %32, %33, 1, 1, 1, %34, %35;"
        : "+f"(d[0]), "+f"(d[1]), "+f"(d[2]), "+f"(d[3]), "+f"(d[4]), "+f"(d[5]), "+f"(d[6]), "+f"(d[7]), "+f"(d[8]), "+f"(d[9]), "+f"(d[10]), "+f"(d[11]), "+f"(d[12]), "+f"(d[13]), "+f"(d[14]), "+f"(d[15]), "+f"(d[16]), "+f"(d[17]), "+f"(d[18]), "+f"(d[19]), "+f"(d[20]), "+f"(d[21]), "+f"(d[22]), "+f"(d[23]), "+f"(d[24]), "+f"(d[25]), "+f"(d[26]), "+f"(d[27]), "+f"(d[28]), "+f"(d[29]), "+f"(d[30]), "+f"(d[31])
        : "l"(da), "l"(db), "n"(TA), "n"(TB));
}

template <int TA, int TB> __device__ __forceinline__ void wgmma_ss_n8(float (&d)[4], uint64_t da, uint64_t db) {
    asm volatile("wgmma.mma_async.sync.aligned.m64n8k16.f32.bf16.bf16 {%0, %1, %2, %3}, %4, %5, 1, 1, 1, %6, %7;"
        : "+f"(d[0]), "+f"(d[1]), "+f"(d[2]), "+f"(d[3])
        : "l"(da), "l"(db), "n"(TA), "n"(TB));
}

template <int TA, int TB> __device__ __forceinline__ void wgmma_ssz_n64(float (&d)[32], uint64_t da, uint64_t db) {
    asm volatile("wgmma.mma_async.sync.aligned.m64n64k16.f32.bf16.bf16 {%0, %1, %2, %3, %4, %5, %6, %7, %8, %9, %10, %11, %12, %13, %14, %15, %16, %17, %18, %19, %20, %21, %22, %23, %24, %25, %26, %27, %28, %29, %30, %31}, %32, %33, 0, 1, 1, %34, %35;"
        : "=f"(d[0]), "=f"(d[1]), "=f"(d[2]), "=f"(d[3]), "=f"(d[4]), "=f"(d[5]), "=f"(d[6]), "=f"(d[7]), "=f"(d[8]), "=f"(d[9]), "=f"(d[10]), "=f"(d[11]), "=f"(d[12]), "=f"(d[13]), "=f"(d[14]), "=f"(d[15]), "=f"(d[16]), "=f"(d[17]), "=f"(d[18]), "=f"(d[19]), "=f"(d[20]), "=f"(d[21]), "=f"(d[22]), "=f"(d[23]), "=f"(d[24]), "=f"(d[25]), "=f"(d[26]), "=f"(d[27]), "=f"(d[28]), "=f"(d[29]), "=f"(d[30]), "=f"(d[31])
        : "l"(da), "l"(db), "n"(TA), "n"(TB));
}

template <int TA, int TB> __device__ __forceinline__ void wgmma_ssz_n8(float (&d)[4], uint64_t da, uint64_t db) {
    asm volatile("wgmma.mma_async.sync.aligned.m64n8k16.f32.bf16.bf16 {%0, %1, %2, %3}, %4, %5, 0, 1, 1, %6, %7;"
        : "=f"(d[0]), "=f"(d[1]), "=f"(d[2]), "=f"(d[3])
        : "l"(da), "l"(db), "n"(TA), "n"(TB));
}


__device__ __forceinline__ void load_blk(uint32_t (&a)[16], const uint4* p) {
#pragma unroll
    for (int k = 0; k < 4; k++) { const uint4 v = ld_ll(p + k * 128); a[4 * k] = v.x; a[4 * k + 1] = v.y; a[4 * k + 2] = v.z; a[4 * k + 3] = v.w; }
}
#define BLK_IO(a) "+r"(a[0]), "+r"(a[1]), "+r"(a[2]), "+r"(a[3]), "+r"(a[4]), "+r"(a[5]), "+r"(a[6]), "+r"(a[7]), \
                  "+r"(a[8]), "+r"(a[9]), "+r"(a[10]), "+r"(a[11]), "+r"(a[12]), "+r"(a[13]), "+r"(a[14]), "+r"(a[15])
#define BLK_LD LD128("%0", "%1", "%2", "%3", "%16") LD128("%4", "%5", "%6", "%7", "%16+2048") LD128("%8", "%9", "%10", "%11", "%16+4096") LD128("%12", "%13", "%14", "%15", "%16+6144")
__device__ __forceinline__ void fix_tag(uint32_t (&a)[16], const uint4* p, uint32_t tag) {
    asm volatile("{ .reg .pred q; .reg .u32 n, m, u; .reg .b128 t; .reg .b64 l, h, w; mov.u32 n, 16384;\n"
                 "C%=: lop3.b32 m, %0, %4, %17, 0x7e; lop3.b32 u, %8, %12, %17, 0x7e; lop3.b32 m, m, u, 1, 0xa8; setp.ne.u32 q, m, 0; vote.sync.any.pred q, q, 0xffffffff; @!q bra.uni D%=;\n"
                 "or.b64 w, %16, 496;\n"
                 "P%=: setp.eq.u32 q, n, 0; @q bra.uni D%=; sub.u32 n, n, 1;\n"
                 "ld.relaxed.gpu.global.u32 m, [w+6144]; lop3.b32 m, m, %17, 1, 0x28; setp.ne.u32 q, m, 0; @q bra.uni P%=;\n"
                 BLK_LD "bra.uni C%=;\n"
                 "D%=: }" : BLK_IO(a) : "l"(p), "r"(tag) : "memory");
}
__device__ __forceinline__ void load_valid(uint32_t (&a)[16], const uint4* p, uint32_t tag) {
    asm volatile("{ .reg .pred q; .reg .u32 n, m, u; .reg .b128 t; .reg .b64 l, h; mov.u32 n, 16384;\n"
                 "C%=: " BLK_LD
                 "lop3.b32 m, %0, %4, %17, 0x7e; lop3.b32 u, %8, %12, %17, 0x7e; lop3.b32 m, m, u, 1, 0xa8; setp.ne.u32 q, m, 0; vote.sync.any.pred q, q, 0xffffffff;\n"
                 "sub.u32 n, n, 1; setp.ne.and.u32 q, n, 0, q; @q bra.uni C%=; }"
                 : "=r"(a[0]), "=r"(a[1]), "=r"(a[2]), "=r"(a[3]), "=r"(a[4]), "=r"(a[5]), "=r"(a[6]), "=r"(a[7]),
                   "=r"(a[8]), "=r"(a[9]), "=r"(a[10]), "=r"(a[11]), "=r"(a[12]), "=r"(a[13]), "=r"(a[14]), "=r"(a[15]) : "l"(p), "r"(tag) : "memory");
}
__device__ __forceinline__ void fix_kv(uint32_t (&v)[32], const uint4* p, uint32_t tag) {
    asm volatile("{ .reg .pred q, p; .reg .u32 n, m, u; .reg .b128 t; .reg .b64 l, h; mov.u32 n, 16384;\n"
                 "L%=: lop3.b32 m, %0, %4, %33, 0x7e; lop3.b32 u, %8, %12, %33, 0x7e; or.b32 m, m, u; lop3.b32 u, %16, %20, %33, 0x7e; or.b32 m, m, u;\n"
                 "lop3.b32 u, %24, %28, %33, 0x7e; lop3.b32 m, m, u, 1, 0xa8; setp.ne.u32 q, m, 0; vote.sync.any.pred q, q, 0xffffffff;\n"
                 "sub.u32 n, n, 1; setp.ne.and.u32 q, n, 0, q; @!q bra.uni D%=;\n"
                 "lop3.b32 m, %0, %33, 1, 0x28; setp.ne.u32 p, m, 0; vote.sync.any.pred p, p, 0xffffffff; @!p bra.uni S0%=; " LD128("%0", "%1", "%2", "%3", "%32+0") "S0%=:\n"
                 "lop3.b32 m, %4, %33, 1, 0x28; setp.ne.u32 p, m, 0; vote.sync.any.pred p, p, 0xffffffff; @!p bra.uni S1%=; " LD128("%4", "%5", "%6", "%7", "%32+2304") "S1%=:\n"
                 "lop3.b32 m, %8, %33, 1, 0x28; setp.ne.u32 p, m, 0; vote.sync.any.pred p, p, 0xffffffff; @!p bra.uni S2%=; " LD128("%8", "%9", "%10", "%11", "%32+4608") "S2%=:\n"
                 "lop3.b32 m, %12, %33, 1, 0x28; setp.ne.u32 p, m, 0; vote.sync.any.pred p, p, 0xffffffff; @!p bra.uni S3%=; " LD128("%12", "%13", "%14", "%15", "%32+6912") "S3%=:\n"
                 "lop3.b32 m, %16, %33, 1, 0x28; setp.ne.u32 p, m, 0; vote.sync.any.pred p, p, 0xffffffff; @!p bra.uni S4%=; " LD128("%16", "%17", "%18", "%19", "%32+9216") "S4%=:\n"
                 "lop3.b32 m, %20, %33, 1, 0x28; setp.ne.u32 p, m, 0; vote.sync.any.pred p, p, 0xffffffff; @!p bra.uni S5%=; " LD128("%20", "%21", "%22", "%23", "%32+11520") "S5%=:\n"
                 "lop3.b32 m, %24, %33, 1, 0x28; setp.ne.u32 p, m, 0; vote.sync.any.pred p, p, 0xffffffff; @!p bra.uni S6%=; " LD128("%24", "%25", "%26", "%27", "%32+13824") "S6%=:\n"
                 "lop3.b32 m, %28, %33, 1, 0x28; setp.ne.u32 p, m, 0; vote.sync.any.pred p, p, 0xffffffff; @!p bra.uni S7%=; " LD128("%28", "%29", "%30", "%31", "%32+16128") "S7%=:\n"
                 "bra.uni L%=;\n D%=: }"
                 : "+r"(v[0]), "+r"(v[1]), "+r"(v[2]), "+r"(v[3]), "+r"(v[4]), "+r"(v[5]), "+r"(v[6]), "+r"(v[7]), "+r"(v[8]), "+r"(v[9]), "+r"(v[10]), "+r"(v[11]), "+r"(v[12]), "+r"(v[13]), "+r"(v[14]), "+r"(v[15]), "+r"(v[16]), "+r"(v[17]), "+r"(v[18]), "+r"(v[19]), "+r"(v[20]), "+r"(v[21]), "+r"(v[22]), "+r"(v[23]), "+r"(v[24]), "+r"(v[25]), "+r"(v[26]), "+r"(v[27]), "+r"(v[28]), "+r"(v[29]), "+r"(v[30]), "+r"(v[31])
                 : "l"(p), "r"(tag) : "memory");
}
__device__ __forceinline__ int wg_tid() { int l; asm volatile("mov.u32 %0, %%tid.x;" : "=r"(l)); return l & 127; }
__device__ __forceinline__ int lane_id() { int l; asm volatile("mov.u32 %0, %%laneid;" : "=r"(l)); return l; }
__device__ __forceinline__ void put_blk(uint4* p, const uint32_t (&a)[16]) {
#pragma unroll
    for (int k = 0; k < 4; k++) st_ll(p + k * 128, a[4 * k], a[4 * k + 1], a[4 * k + 2], a[4 * k + 3]);
}
__device__ __forceinline__ void quad_t(uint32_t& a0, uint32_t& a1, uint32_t& a2, uint32_t& a3, int t) {
    const bool p = t & 1, q = t & 2;
    uint32_t r0 = __shfl_xor_sync(~0u, p ? a0 : a1, 1), r1 = __shfl_xor_sync(~0u, p ? a2 : a3, 1);
    a0 = p ? r0 : a0; a1 = p ? a1 : r0; a2 = p ? r1 : a2; a3 = p ? a3 : r1;
    r0 = __shfl_xor_sync(~0u, q ? a0 : a2, 2); r1 = __shfl_xor_sync(~0u, q ? a1 : a3, 2);
    a0 = q ? r0 : a0; a2 = q ? a2 : r0; a1 = q ? r1 : a1; a3 = q ? a3 : r1;
}
template <int N> __device__ __forceinline__ void strip_sum(const uint4 (&w)[N], uint32_t dst, uint32_t bar) {
    float cs[4][4];
#pragma unroll
    for (int k = 0; k < 16; k++) cs[k >> 2][k & 3] = 0.f;
#pragma unroll
    for (int k = 0; k < N; k += 2) {
        colsum16(cs[0], w[k].x, w[k + 1].x); colsum16(cs[1], w[k].y, w[k + 1].y);
        colsum16(cs[2], w[k].z, w[k + 1].z); colsum16(cs[3], w[k].w, w[k + 1].w);
    }
    const int l = lane_id();
    if (l < 4) {
#pragma unroll
        for (int k = 0; k < 2; k++)
            asm volatile("st.shared.v4.f32 [%0], {%1,%2,%3,%4};" ::"r"(dst + l * 32 + k * 16), "f"(cs[2 * k][0]), "f"(cs[2 * k][1]), "f"(cs[2 * k + 1][0]), "f"(cs[2 * k + 1][1]) : "memory");
    }
    __syncwarp();
    if (l < N / 4) mbar_arrive(bar);
}
__device__ __forceinline__ void put_stats(const uint32_t (&x)[16], uint4* p, uint32_t tag) {
    float s0 = 0.f, q0 = 0.f, s1 = 0.f, q1 = 0.f;
#pragma unroll
    for (int i = 0; i < 16; i += 2) {
        const float a = lo_f(x[i]), b = hi_f(x[i]), c = lo_f(x[i + 1]), d = hi_f(x[i + 1]);
        s0 += a + b; q0 = fmaf(a, a, fmaf(b, b, q0));
        s1 += c + d; q1 = fmaf(c, c, fmaf(d, d, q1));
    }
#pragma unroll
    for (int m = 1; m < 4; m <<= 1) {
        s0 += __shfl_xor_sync(~0u, s0, m); q0 += __shfl_xor_sync(~0u, q0, m);
        s1 += __shfl_xor_sync(~0u, s1, m); q1 += __shfl_xor_sync(~0u, q1, m);
    }
    if ((lane_id() & 3) == 0) st_ll(p, tg(fu(s0), tag), fu(q0), fu(s1), fu(q1));
}
__device__ __forceinline__ void get_stats(uint4 u, uint4 v, const uint4* p, uint32_t tag, float& m0, float& m1, float& r0, float& r1) {
#pragma unroll 1
    for (int n = 0; n < SPIN_MAX && __any_sync(~0u, ((u.x ^ tag) | (v.x ^ tag)) & 1); n++) { u = ld_ll(p); v = ld_ll(p + 1); }
    float s0 = uf(u.x) + uf(v.x), q0 = uf(u.y) + uf(v.y), s1 = uf(u.z) + uf(v.z), q1 = uf(u.w) + uf(v.w);
#pragma unroll
    for (int m = 1; m < 4; m <<= 1) {
        s0 += __shfl_xor_sync(~0u, s0, m); q0 += __shfl_xor_sync(~0u, q0, m);
        s1 += __shfl_xor_sync(~0u, s1, m); q1 += __shfl_xor_sync(~0u, q1, m);
    }
    m0 = s0 * (-1.f / D_); m1 = s1 * (-1.f / D_);
    r0 = rsqrtf(fmaxf(fmaf(-m0, m0, q0 * (1.f / D_)), 0.f) + 1e-5f);
    r1 = rsqrtf(fmaxf(fmaf(-m1, m1, q1 * (1.f / D_)), 0.f) + 1e-5f);
}
__device__ __forceinline__ void poll7(const uint4* p, int c, uint32_t tag) {
    const int l = min(lane_id(), 6);
    const uint32_t* w = reinterpret_cast<const uint32_t*>((reinterpret_cast<uintptr_t>(p) | 496) + 6144 + (l + (l >= c)) * 8192);
#pragma unroll 1
    for (int n = 0; n < SPIN_MAX; n++) {
        uint32_t v; asm volatile("ld.relaxed.gpu.global.u32 %0, [%1];" : "=r"(v) : "l"(w) : "memory");
        if (!__any_sync(~0u, (v ^ tag) & 1)) break;
    }
}
__device__ __forceinline__ void poll1(const uint4* p, uint32_t tag) {
    const uint32_t* w = reinterpret_cast<const uint32_t*>(reinterpret_cast<uintptr_t>(p) | 496);
#pragma unroll 1
    for (int n = 0; n < SPIN_MAX; n++) {
        uint32_t v; asm volatile("ld.relaxed.gpu.global.u32 %0, [%1];" : "=r"(v) : "l"(w) : "memory");
        if (!__any_sync(~0u, (v ^ tag) & 1)) break;
    }
}
__device__ __forceinline__ void load_hid(uint32_t (&a)[56], const uint4* p) {
#pragma unroll
    for (int k = 0; k < 14; k++) { const uint4 v = ld_ll(p + k * 128); a[4 * k] = v.x; a[4 * k + 1] = v.y; a[4 * k + 2] = v.z; a[4 * k + 3] = v.w; }
}
__device__ __forceinline__ void fix_hid(uint32_t (&a)[56], const uint4* p, uint32_t tag) {
#pragma unroll 1
    for (int n = 0; n < 1024; n++) {
        uint32_t m = 0;
#pragma unroll
        for (int k = 0; k < 14; k += 2) m |= nae(a[4 * k], a[4 * k + 4], tag);
        if (!__any_sync(~0u, m & 1)) break;
        poll1(p + 13 * 128, tag);
        load_hid(a, p);
    }
}
__device__ __forceinline__ void pin(uint32_t bar) { asm volatile("{ .reg .pred p; mbarrier.test_wait.parity.shared::cta.b64 p, [%0], 0; }" ::"r"(bar) : "memory"); }
__device__ __forceinline__ uint32_t bad_blk(const uint32_t (&a)[16], uint32_t tag) { return nae(a[0], a[4], tag) | nae(a[8], a[12], tag); }
__device__ __forceinline__ void ptr7(const uint4* (&q)[8], const uint4* p, int c) {
#pragma unroll
    for (int i = 1; i < 8; i++) { q[i] = p + KB(i) * 512; asm volatile("" : "+l"(q[i])); }
}
__device__ __forceinline__ void gather7(uint32_t (&X)[8][16], const uint4* (&q)[8]) {
#pragma unroll
    for (int i = 1; i < 8; i++) load_blk(X[i], q[i]);
}
__device__ __forceinline__ bool wg_any(uint32_t bad, int wg) {
    uint32_t r;
    asm volatile("{ .reg .pred p, q; setp.ne.u32 q, %1, 0; barrier.red.or.pred.aligned p, %2, 128, q; selp.u32 %0, 1, 0, p; }" : "=r"(r) : "r"(bad & 1), "r"(5 + wg) : "memory");
    return __any_sync(~0u, r);
}

struct Maps { CUtensorMap m[6]; };

__global__ void __cluster_dims__(2, 1, 1) __launch_bounds__(384, 1)
fused_kernel(Xchg* __restrict__ const Gp, const __nv_bfloat16* __restrict__ wqkv, const __nv_bfloat16* __restrict__ wo,
             const __nv_bfloat16* __restrict__ w1, const __nv_bfloat16* __restrict__ b1, const __nv_bfloat16* __restrict__ w2,
             const __nv_bfloat16* __restrict__ b2, __nv_bfloat16* __restrict__ out, const __grid_constant__ Maps maps) {
    extern __shared__ __align__(1024) uint8_t smem[];
    Xchg& G = *Gp;
    const int rank = blockIdx.x & 1;
    const uint32_t SC = rank << 24;
    const int warp = __shfl_sync(0xffffffffu, (int)(threadIdx.x >> 5), 0), lane = threadIdx.x & 31;
    if (threadIdx.x == 64) {
#pragma unroll
        for (int i = 0; i < 6; i++) asm volatile("prefetch.tensormap [%0];" ::"l"(&maps.m[(i + 5) % 6]) : "memory");
    }
    if (threadIdx.x == 0) {
#pragma unroll
        for (int i = 0; i < 8; i++) { mbar_init(SC + FULL + i * 8, 1); mbar_init(SC + EMPTY + i * 8, 16); }
#pragma unroll
        for (int i = 4; i < 8; i++) mbar_init(SC + XBAR + i * 8, 1);
        mbar_init(SC + KVBAR, 10); mbar_init(SC + CSBAR, 2); mbar_init(SC + CPBAR, 8); mbar_init(SC + W1BAR, 1);
        asm volatile("fence.mbarrier_init.release.cluster;" ::: "memory");
    }
    __syncwarp();
    asm volatile("barrier.cluster.arrive.relaxed.aligned;" ::: "memory");
    const int cj = blockIdx.x >> 1;
    const int cu = cj - 36, grp = cj < 4 ? 0 : cj < 36 ? (cj & 7) : (cu % 7 + 3) % 7 + 1;
    const int rg = 2 * grp + rank;
    const int c = cj < 4 ? cj : cj < 36 ? ((cj & 7) ? (cj - 4) >> 3 : 3 + (cj >> 3)) : 4 + cu / 7;
    const int g = lane >> 2, t = lane & 3;
    if ((warp >> 2) == 1) {
        const uint32_t xb = SC + XBAR + (warp - 4) * 8;
        asm volatile("{ .reg .pred p; elect.sync _|p, 0xffffffff; @p mbarrier.init.shared::cta.b64 [%0], 1; fence.proxy.async.shared::cta;\n"
                     "@p mbarrier.arrive.expect_tx.shared::cta.b64 _, [%0], 16384; }" ::"r"(xb) : "memory");
#pragma unroll 1
        for (int q = 0; q < 4; q++)
            asm volatile("{ .reg .pred p; elect.sync _|p, 0xffffffff;\n"
                         "@p cp.async.bulk.tensor.3d.shared::cluster.global.mbarrier::complete_tx::bytes [%0], [%1, {%3, %4, %5}], [%2]; }"
                         ::"r"(SC + xunit((warp - 4) * 4 + q)), "l"(&maps.m[5]), "r"(xb), "r"(0), "r"(rg * 128 + (warp - 4) * 16), "r"(2 * q) : "memory");
        __syncwarp();
        asm volatile("bar.arrive 9, 288;" ::: "memory");
    }
    pair_wait();
    uint32_t eb;
    asm("mapa.shared::cluster.u32 %0, %1, %2;" : "=r"(eb) : "r"(EMPTY), "r"((rank ^ lane) & 1));
    const bool l0 = lane < 2;
    if (((uint32_t)__cvta_generic_to_shared(smem) & 0xffffffu) != SB) return;

    if (warp >= 4) {
        asm volatile("setmaxnreg.inc.sync.aligned.u32 232;");
        uint4 cw[8];
        if (warp >= 8) {
            const int j = min(rg >> 1, 5);
            const uint4* wp = reinterpret_cast<const uint4*>(wqkv) + (j < 4 ? 64 + (j >> 1) * 64 : 0) + 8 * c + 4 * (j & 1) + ((rg & 1) * 256 + (warp - 8) * 64 + g) * 192 + t;
#pragma unroll
            for (int k = 0; k < 8; k++) cw[k] = __ldg(wp + k * 8 * 192);
        } else {
#pragma unroll
            for (int k = 0; k < 8; k++) cw[k] = make_uint4(0u, 0u, 0u, 0u);
        }
        if (warp >= 8) {
            asm volatile("bar.sync 9, 288;" ::: "memory");
            const uint32_t xb = SC + XBAR + (warp - 4) * 8;
            asm volatile("{ .reg .pred p; elect.sync _|p, 0xffffffff; @p mbarrier.arrive.expect_tx.shared::cta.b64 _, [%0], 16384; }" ::"r"(xb) : "memory");
#pragma unroll 1
            for (int q = 0; q < 4; q++)
                asm volatile("{ .reg .pred p; elect.sync _|p, 0xffffffff;\n"
                             "@p cp.async.bulk.tensor.3d.shared::cluster.global.mbarrier::complete_tx::bytes [%0], [%1, {%3, %4, %5}], [%2]; }"
                             ::"r"(SC + xunit((warp - 4) * 4 + q)), "l"(&maps.m[5]), "r"(xb), "r"(0), "r"(rg * 128 + (warp - 4) * 16), "r"(2 * q) : "memory");
        }
        const int wg = (warp >> 2) - 1, wl = warp & 3;
        if (warp >= 8) strip_sum<8>(cw, SC + P_CS + (warp - 8) * 128, SC + CPBAR);
        if (threadIdx.x == 256) {
            l2_prefetch(reinterpret_cast<const char*>(wqkv) + blockIdx.x * 12288, 12288);
            l2_prefetch(reinterpret_cast<const char*>(wo) + blockIdx.x * 4096, 4096);
            l2_prefetch(reinterpret_cast<const char*>(w1) + blockIdx.x * 14336, 14336);
        }
        release(eb, 6, l0 && wg); release(eb, 7, l0 && wg);
        uint32_t xr[16];
        const uint32_t xl = SC + (lane & 15) * 128 + (((lane >> 4) ^ (lane & 7)) << 4);
        mbar_wait(SC + XBAR + (warp - 4) * 8, 0);
#pragma unroll
        for (int k = 0; k < 4; k++) ldsm4(xr + 4 * k, (xl ^ (k * 32)) + xunit((warp - 4) * 4 + (c >> 1)) + (c & 1) * 2048);
        uint32_t raw[4];
#pragma unroll
        for (int k = 0; k < 4; k++) raw[k] = xr[4 * k];
#pragma unroll 1
        for (int hl = 0; hl < 4; hl++) {
            const uint32_t tag = 1 - (hl >> 1);
            uint4* const px = &G.r[rg].x[hl & 1][wg][0][0][wg_tid()];
            uint4* const pst = &G.r[rg].st[hl & 1][wg][wl][g][0];
            uint32_t flip = 0;
#pragma unroll
            for (int k = 0; k < 4; k++) flip |= (xr[4 * k] ^ raw[k]) << k;
            asm volatile("" : "+r"(flip));
            uint4* pub;
            uint32_t tagn;
            float m0, m1, r0, r1;
            float y[32];
            if (!(hl & 1)) {
                uint32_t X[8][16];
                uint32_t pq[16], v[32];
                const uint4* pk;
                {
                    float ak[32], av[32];
                    uint4 su, sv;
                    float e0, e1;
                    uint32_t stg, cqa;
#define KVD(i, k) mkdesc(SB + (i) * SLOT + ((k) >> 1) * 8192 + ((k) & 1) * 2048, 4096, 1024, 1)
#pragma unroll 1
                    for (int n = 0;; n++) {
                        mbar_wait(SC + FULL, 0);
                        wg_fence();
                        wgmma_rsz_n64(ak, xr, KVD(0, 0));
#pragma unroll
                        for (int k = 1; k < 4; k++) wgmma_rs_n64(ak, xr + 4 * k, KVD(0, k));
                        wg_commit();
                        if (hl) {
                            put_stats(xr, pst + c, tag);
                            mbar_wait(SC + FULL + 8, 0); mbar_wait2(SC + FULL + 16, 0);
                            const uint4* q[8];
                            ptr7(q, px, c);
                            poll7(px, c, tag);
                            if (wg == 1 && n == 0) asm volatile("bar.sync 4, 256;" ::: "memory");
                            gather7(X, q);
                            if (wg == 0 && n == 0) asm volatile("bar.arrive 4, 256;" ::: "memory");
                        } else {
                            const int ln = lane_id();
                            const uint32_t xa = SC + (ln & 15) * 128 + (((ln >> 4) ^ (ln & 7)) << 4);
                            const int kb = KB(ln & 7);
                            const uint32_t tab = xunit((warp - 4) * 4 + (kb >> 1)) + (kb & 1) * 2048;
#pragma unroll
                            for (int i = 1; i < 8; i++) {
                                const uint32_t ad = xa + __shfl_sync(~0u, tab, i);
#pragma unroll
                                for (int k = 0; k < 4; k++) ldsm4(X[i] + 4 * k, ad ^ (k * 32));
                            }
                            mbar_wait(SC + FULL + 8, 0);
                            put_stats(xr, pst + c, tag);
                            uint32_t dep = 0;
#pragma unroll
                            for (int i = 1; i < 8; i++) dep |= (X[i][1] | X[i][5]) | (X[i][9] | X[i][13]);
                            dep &= (uint32_t)reinterpret_cast<uintptr_t>(out) & 1u;
                            release(eb + dep, 6, l0 && !wg); release(eb + dep, 7, l0 && !wg);
                            if (wg) asm volatile("bar.arrive %0, 256;" ::"r"(8 + dep) : "memory");
                            mbar_wait2(SC + FULL + 16, 0);
                        }
#pragma unroll
                        for (int i = 1; i < 8; i++) {
                            if (i == 4 || i == 6) mbar_wait2(SC + FULL + i * 8, 0);
                            if (i == 6) { su = ld_ll(pst + 2 * t); sv = ld_ll(pst + 2 * t + 1); }
                            wg_fence();
#pragma unroll
                            for (int k = 0; k < 4; k++) wgmma_rs_n64(ak, X[i] + 4 * k, KVD(i, k));
                        }
                        wg_commit();
                        wgmma_rsz_n64(av, xr, KVD(0, 0) + 256);
#pragma unroll
                        for (int k = 1; k < 8; k++) wgmma_rs_n64(av, (k < 4 ? xr : X[1]) + 4 * (k & 3), KVD(k >> 2, k & 3) + 256);
                        wg_commit();
                        get_stats(su, sv, pst + 2 * t, tag, m0, m1, r0, r1);
                        e0 = r0 * 1.4426950408889634f; e1 = r1 * 1.4426950408889634f;
                        {
                            const int ln = lane_id();
                            stg = SC + P_STG + wg * 2 * SLOT + (wl * 16 + (ln & 15)) * 128 + (((ln >> 4) ^ (ln & 7)) << 4);
                            cqa = SC + SM_CQ + (ln & 3) * 8;
                        }
                        asm volatile("" : "+f"(m0), "+f"(m1), "+f"(r0), "+f"(r1), "+f"(e0), "+f"(e1), "+r"(stg), "+r"(cqa));
                        mbar_wait(SC + CSBAR, 0);
                        uint32_t bad = 0;
#pragma unroll
                        for (int i = 1; i < 8; i++) bad |= bad_blk(X[i], tag);
                        const bool again = wg_any(bad & (hl >> 1), wg);
                        wg_wait<1>();
                        keep(ak);
                        if (!again || n > 64) break;
                        wg_wait<0>();
                        keep(av);
                    }
                    wg_fence();
#pragma unroll
                    for (int j = 0; j < 8; j++) wgmma_rs_n64(av, X[2 + (j >> 2)] + 4 * (j & 3), KVD(2 + (j >> 2), j & 3) + 256);
                    wg_commit();
                    if (hl + wg == 0) asm volatile("bar.sync 8, 256;" ::: "memory");
                    const int lane = lane_id(), t = lane & 3, g = lane >> 2;
#pragma unroll
                    for (int k = 0; k < 4; k++) {
                        if (k < 3) {
                            if (k)
                            {
                            wg_fence();
#pragma unroll
                            for (int j = 0; j < 8; j++) wgmma_rs_n64(av, X[2 * k + 2 + (j >> 2)] + 4 * (j & 3), KVD(2 * k + 2 + (j >> 2), j & 3) + 256);
                            wg_commit();
                            }
                            wg_wait<1>();
                            release(eb, 2 * k, l0); release(eb, 2 * k + 1, l0);
                        }
                        const uint32_t ad = stg ^ (k * 32);
                        const float* kk = &ak[8 * k];
                        const float2 c0 = lds2(cqa + k * 64), c1 = lds2(cqa + k * 64 + 32);
                        stsm4(ad, pack2(phi(fmaf(m0, c0.x, kk[0]), r0, e0), phi(fmaf(m0, c0.y, kk[1]), r0, e0)),
                              pack2(phi(fmaf(m1, c0.x, kk[2]), r1, e1), phi(fmaf(m1, c0.y, kk[3]), r1, e1)),
                              pack2(phi(fmaf(m0, c1.x, kk[4]), r0, e0), phi(fmaf(m0, c1.y, kk[5]), r0, e0)),
                              pack2(phi(fmaf(m1, c1.x, kk[6]), r1, e1), phi(fmaf(m1, c1.y, kk[7]), r1, e1)));
                    }
                    wg_wait<0>();
                    keep(av);
#pragma unroll
                    for (int k = 0; k < 4; k++) {
                        const uint32_t ad = stg ^ (k * 32);
                        const float* vv = &av[8 * k];
                        const float2 c0 = lds2(cqa + 256 + k * 64), c1 = lds2(cqa + 256 + k * 64 + 32);
                        stsm4(ad + SLOT, pack2(fmaf(m0, c0.x, vv[0]) * r0, fmaf(m0, c0.y, vv[1]) * r0), pack2(fmaf(m1, c0.x, vv[2]) * r1, fmaf(m1, c0.y, vv[3]) * r1),
                              pack2(fmaf(m0, c1.x, vv[4]) * r0, fmaf(m0, c1.y, vv[5]) * r0), pack2(fmaf(m1, c1.x, vv[6]) * r1, fmaf(m1, c1.y, vv[7]) * r1));
                    }
                    if (wg == 0 && wl < 2) asm volatile("st.shared.u32 [%0], %1;" ::"r"(SC + P_ONES + wl * 128 + lane * 4), "r"(0x3f803f80u) : "memory");
                    asm volatile("fence.proxy.async.shared::cta;" ::: "memory");
                    if (wg == 1) {
                        asm volatile("bar.arrive 1, 256;" ::: "memory");
                    } else {
                        asm volatile("bar.sync 10, 128;" ::: "memory");
                        float kv[32], z[4];
                        wg_fence();
#pragma unroll
                        for (int k = 0; k < 8; k++) {
                            constexpr uint64_t d0 = mkdesc(P_STG, 8192, 1024, 1);
                            const uint64_t dk = d0 + (k >> 2) * (SLOT / 8) + (k & 3) * 128;
                            constexpr uint64_t d1 = mkdesc(P_ONES, 128, 128, 0);
                            if (k == 4) { wg_commit(); asm volatile("bar.sync 1, 256;" ::: "memory"); wg_fence(); }
                            if (k) { wgmma_ss_n64<1, 1>(kv, dk + SLOT / 16, dk); wgmma_ss_n8<1, 0>(z, dk, d1); }
                            else { wgmma_ssz_n64<1, 1>(kv, dk + SLOT / 16, dk); wgmma_ssz_n8<1, 0>(z, dk, d1); }
                        }
                        wg_commit();
                        wg_wait<0>();
                        keep(kv); keep(z);
                        float w8[8];
#pragma unroll
                        for (int j = 0; j < 8; j++) w8[j] = (wl & 2) ? ((wl & 1) ? kv[24 + j] : kv[16 + j]) : ((wl & 1) ? kv[8 + j] : kv[j]);
                        st_ll(&G.kvp[c][rg][wg_tid()], tg(pack2(w8[0], w8[1]), tag), pack2(w8[4], w8[5]), pack2(w8[2], w8[3]), pack2(w8[6], w8[7]));
                        if (t == 0) {
                            uint32_t* pz = reinterpret_cast<uint32_t*>(&G.kvp[c][rg][128]) + wl * 16 + g;
                            st_ll1(pz, tg(fu(z[0]), tag)); st_ll1(pz + 8, tg(fu(z[2]), tag));
                        }
                        asm volatile("bar.arrive 2, 192;" ::: "memory");
                    }
                    release(eb, 6, l0); release(eb, 7, l0);
#pragma unroll
                    for (int i = 0; i < 8; i++) {
                        const uint32_t* A = i ? X[i] : xr;
                        if (i % 2 == 0) mbar_wait(SC + FULL + (i / 2) * 8, 1);
                        if (i % 2 == 0) wg_fence();
#pragma unroll
                        for (int k = 0; k < 4; k++) {
                            const uint64_t db = mkdesc(SB + (i / 2) * SLOT + (i % 2) * 8192 + k * 2048, 8192, 1024, 1);
                            if (i | k) wgmma_rs_n64(y, A + 4 * k, db); else wgmma_rsz_n64(y, A, db);
                        }
                    }
                    wg_commit();
                    wg_wait<0>();
                    keep(y);
                    pk = &G.kvp[c][(lane >> 4) * 8][wg * 64 + wl * 16 + (lane & 15)];
#pragma unroll
                    for (int j = 0; j < 8; j++) { const uint4 u = ld_ll(pk + j * 144); v[4 * j] = u.x; v[4 * j + 1] = u.y; v[4 * j + 2] = u.z; v[4 * j + 3] = u.w; }
                    release(eb, 0, l0); release(eb, 1, l0); release(eb, 2, l0); release(eb, 3, l0);
#pragma unroll
                    for (int j = 0; j < 8; j++) {
                        const float2 cq = lds2(cqa + 512 + j * 32);
                        pq[2 * j] = pack2(phi(fmaf(m0, cq.x, y[4 * j]), r0, e0), phi(fmaf(m0, cq.y, y[4 * j + 1]), r0, e0));
                        pq[2 * j + 1] = pack2(phi(fmaf(m1, cq.x, y[4 * j + 2]), r1, e1), phi(fmaf(m1, cq.y, y[4 * j + 3]), r1, e1));
                    }
                }
                const int lane = lane_id(), t = lane & 3;
                {
                    uint32_t dep = 0;
#pragma unroll
                    for (int k = 0; k < 16; k++) dep |= pq[k];
                    fix_kv(v, pk, tag | (dep & (uint32_t)reinterpret_cast<uintptr_t>(out) & 1u));
                    const uint32_t id = t == lane >> 3 ? 0x3f80u << (lane & 4) * 4 : 0u;
                    float s[16];
#pragma unroll
                    for (int j = 0; j < 16; j++) s[j] = 0.f;
#pragma unroll
                    for (int j = 0; j < 8; j++) { acc_bf(s + (j & 1) * 8, v[4 * j], v[4 * j + 1], id); acc_bf(s + 4 + (j & 1) * 8, v[4 * j + 2], v[4 * j + 3], id); }
#pragma unroll
                    for (int j = 0; j < 8; j++) { s[j] += s[j + 8]; s[j] += __shfl_xor_sync(~0u, s[j], 16); }
                    if (lane < 16)
                        asm volatile("st.shared.v4.u32 [%0], {%1,%2,%3,%4};" ::"r"(SC + P_KVF + (wg * 64 + wl * 16 + lane) * 16), "r"(pack2(s[0], s[1])), "r"(pack2(s[2], s[3])),
                                     "r"(pack2(s[4], s[5])), "r"(pack2(s[6], s[7])) : "memory");
                    __syncwarp();
                    if (lane == 0) mbar_arrive(SC + KVBAR);
                }
                uint4* po = &G.r[rg].o[wg][c][0][wg_tid()];
                uint32_t ka = SC + P_KVF + lane * 16, za = SC + P_ZF + t * 4;
                asm volatile("" : "+l"(po), "+r"(ka), "+r"(za));
                mbar_wait(SC + KVBAR, hl >> 1);
#pragma unroll
                for (int h = 0; h < 4; h++) {
                    uint32_t b0, b1_, b2_, b3, z0, z1;
                    asm volatile("ld.shared.v4.u32 {%0,%1,%2,%3}, [%4];" : "=r"(b0), "=r"(b1_), "=r"(b2_), "=r"(b3) : "r"(ka + h * 512));
                    asm volatile("ld.shared.u32 %0, [%1];" : "=r"(z0) : "r"(za + h * 32));
                    asm volatile("ld.shared.u32 %0, [%1];" : "=r"(z1) : "r"(za + h * 32 + 16));
                    float n0[4], n1[4], dn[4];
                    mma16816(n0, &pq[4 * h], b0, b1_);
                    mma16816(n1, &pq[4 * h], b2_, b3);
                    mma16816(dn, &pq[4 * h], z0, z1);
                    const float i0 = rcp(dn[0] + 1e-6f), i1 = rcp(dn[2] + 1e-6f);
                    X[0][4 * h] = tg(pack2(n0[0] * i0, n0[1] * i0), tag); X[0][4 * h + 1] = pack2(n0[2] * i1, n0[3] * i1);
                    X[0][4 * h + 2] = pack2(n1[0] * i0, n1[1] * i0); X[0][4 * h + 3] = pack2(n1[2] * i1, n1[3] * i1);
                }
                if (wg == 1) {
                    uint32_t dep = 0;
#pragma unroll
                    for (int k = 0; k < 16; k++) dep |= X[0][k];
                    asm volatile("bar.sync %0, 256;" ::"r"(3 + (dep & (uint32_t)reinterpret_cast<uintptr_t>(out) & 1u)) : "memory");
                }
                put_blk(po, X[0]);
#define WOD(i, k) mkdesc(SB + (4 + (i) / 2) * SLOT + ((i) % 2) * 8192 + (k) * 2048, 8192, 1024, 1)
#pragma unroll 1
                for (int n = 0;; n++) {
                    mbar_wait(SC + FULL + 32, 1);
#pragma unroll
                    for (int j = 0; j < 16; j++) {
                        if (!(j & 3)) asm volatile("" : "+r"(xr[j]), "+r"(xr[j + 1]), "+r"(xr[j + 2]), "+r"(xr[j + 3]), "+r"(flip));
                        const uint32_t w = (j & 3) ? xr[j] : xr[j] ^ ((flip >> (j >> 2)) & 1);
                        y[2 * j] = lo_f(w); y[2 * j + 1] = hi_f(w);
                    }
                    int co = c;
                    asm volatile("" : "+r"(co));
                    const uint4* const pg = po - co * 512;
                    wg_fence();
#pragma unroll
                    for (int k = 0; k < 4; k++) wgmma_rs_n64(y, X[0] + 4 * k, WOD(0, k));
                    wg_commit();
                    mbar_wait(SC + FULL + 40, 1); mbar_wait2(SC + FULL + 48, 1);
                    const uint4* q[8];
                    ptr7(q, pg, co);
                    poll7(pg, co, tag);
                    if (wg == 0 && n == 0) asm volatile("bar.arrive 3, 256;" ::: "memory");
                    gather7(X, q);
                    pin(SC + CSBAR);
#pragma unroll
                    for (int i = 1; i < 8; i++) {
                        if (i == 1 || !(i & 1)) wg_fence();
#pragma unroll
                        for (int k = 0; k < 4; k++) wgmma_rs_n64(y, X[i] + 4 * k, WOD(i, k));
                    }
                    wg_commit();
                    pub = &G.r[rg].x[1][wg][c][0][wg_tid()]; tagn = tag;
                    asm volatile("" : "+l"(pub), "+r"(tagn));
                    mbar_wait(SC + CSBAR, 0);
                    uint32_t bad = 0;
#pragma unroll
                    for (int i = 7; i > 0; i--) bad |= bad_blk(X[i], tag);
                    const bool again = wg_any(bad, wg);
                    wg_wait<0>();
                    keep(y);
                    if (!again || n > 64) break;
                }
            } else {
                uint32_t H[2][56];
                uint4* const phid = &G.r[rg].h[wg][0][0][wg_tid()];
                {
                    float acc[112];
                    uint32_t W[4][16];
                    mbar_wait(SC + FULL, 0);
                    constexpr uint64_t d1 = mkdesc(SB, 2048, 512, 2);
                    wg_fence();
                    wgmma_rsz_n224(acc, xr, d1);
#pragma unroll
                    for (int k = 1; k < 4; k++) wgmma_rs_n224(acc, xr + 4 * k, d1 + (k >> 1) * 896 + (k & 1) * 64);
                    wg_commit();
                    put_stats(xr, pst + c, tag);
                    poll7(px, c, tag);
                    load_blk(W[0], px + KB(1) * 512); load_blk(W[1], px + KB(2) * 512);
                    load_blk(W[2], px + KB(3) * 512); load_blk(W[3], px + KB(4) * 512);
                    uint4 su, sv;
#pragma unroll
                    for (int i = 1; i < 8; i += 2) {
                        const int j = (i >> 1 & 1) * 2;
                        if (i < 7) mbar_wait2(SC + FULL + i * 8, 0); else mbar_wait(SC + FULL + i * 8, 0);
                        fix_tag(W[j], px + KB(i) * 512, tag);
                        if (i < 7) fix_tag(W[j + 1], px + KB(i + 1) * 512, tag);
                        wg_fence();
#pragma unroll
                        for (int k = 0; k < (i < 7 ? 8 : 4); k++)
                            wgmma_rs_n224(acc, W[j + (k >> 2)] + 4 * (k & 3), d1 + (i + (k >> 2)) * (SLOT / 16) + (k >> 1 & 1) * 896 + (k & 1) * 64);
                        wg_commit();
                        wg_wait<1>();
                        release(eb, i - 1, l0);
                        if (i > 1) release(eb, i - 2, l0);
                        if (i > 1 && i < 7) load_blk(W[2 - j], px + KB(i + 2) * 512);
                        if (i > 1 && i < 5) load_blk(W[3 - j], px + KB(i + 3) * 512);
                        if (i == 5) { su = ld_ll(pst + 2 * t); sv = ld_ll(pst + 2 * t + 1); }
                    }
                    get_stats(su, sv, pst + 2 * t, tag, m0, m1, r0, r1);
                    r0 *= 0.5f; r1 *= 0.5f; m0 *= r0; m1 *= r1;
                    uint4* ph = phid + c * 1792;
                    uint32_t ba = SC + SM_B1 + (lane_id() & 3) * 16;
                    asm volatile("" : "+f"(m0), "+f"(m1), "+f"(r0), "+f"(r1), "+l"(ph), "+r"(ba));
                    mbar_wait(SC + W1BAR, 0);
                    wg_wait<0>();
                    keep(acc);
                    release(eb, 7, l0);
#pragma unroll
                    for (int j = 0; j < 28; j++) {
                        const float4 bb = lds4(ba + j * 64);
                        H[0][2 * j] = pack2(gelu2(fmaf(acc[4 * j], r0, fmaf(m0, bb.z, bb.x))), gelu2(fmaf(acc[4 * j + 1], r0, fmaf(m0, bb.w, bb.y))));
                        H[0][2 * j + 1] = pack2(gelu2(fmaf(acc[4 * j + 2], r1, fmaf(m1, bb.z, bb.x))), gelu2(fmaf(acc[4 * j + 3], r1, fmaf(m1, bb.w, bb.y))));
                        if (j & 1) {
                            H[0][2 * j - 2] = tg(H[0][2 * j - 2], tag);
                            st_ll(ph + (j >> 1) * 128, H[0][2 * j - 2], H[0][2 * j - 1], H[0][2 * j], H[0][2 * j + 1]);
                        }
                    }
                }
                float a[64];
                const bool lf = l0 && hl == 1;
                uint4* pp;
#pragma unroll
                for (int i = 0; i < 4; i++) {
                    const uint4* const ps = phid + HS(i) * 1792;
                    mbar_wait2(SC + FULL + i * 16, 1);
                    if (i) fix_hid(H[i & 1], ps, tag);
                    wg_fence();
#pragma unroll
                    for (int k = 0; k < 14; k++) {
                        const uint64_t db = mkdesc(SB + (2 * i + k / 7) * SLOT + (k % 7) * 2048, 14336, 1024, 1);
                        if (i | k) wgmma_rs_n128(a, H[i & 1] + 4 * k, db); else wgmma_rsz_n128(a, H[0], db);
                    }
                    wg_commit();
                    const uint4* const pn = phid + HS(i + 1) * 1792;
                    if (i) { wg_wait<1>(); release(eb, 2 * i - 2, lf); release(eb, 2 * i - 1, lf); }
                    else poll1(pn + 13 * 128, tag);
                    if (i < 3) load_hid(H[(i + 1) & 1], pn);
                    if (i == 2) { pp = &G.r[rg].p[wg][c ^ 1][0][wg_tid()]; asm volatile("" : "+l"(pp)); }
                }
                wg_wait<0>();
                keep(a);
                uint32_t P[16];
#pragma unroll
                for (int j = 0; j < 16; j++) P[j] = pack2(a[32 + 2 * j], a[33 + 2 * j]);
#pragma unroll
                for (int j = 0; j < 16; j += 4) P[j] = tg(P[j], tag);
                put_blk(pp, P);
                release(eb, 6, lf); release(eb, 7, lf);
                pp += ((c & 1) * 2 - 1) * 512;
                mbar_wait(SC + CSBAR, 0);
                const int lane = lane_id();
#pragma unroll
                for (int k = 0; k < 16; k++) asm volatile("" : "+r"(xr[k]));
#pragma unroll
                for (int j = 0; j < 8; j++) {
                    const float2 bb = lds2(SC + SM_B2 + (lane & 3) * 8 + j * 32);
                    const uint32_t w0 = (j & 1) ? xr[2 * j] : xr[2 * j] ^ ((flip >> (j >> 1)) & 1), w1_ = xr[2 * j + 1];
                    y[4 * j] = a[4 * j] + (lo_f(w0) + bb.x); y[4 * j + 1] = a[4 * j + 1] + (hi_f(w0) + bb.y);
                    y[4 * j + 2] = a[4 * j + 2] + (lo_f(w1_) + bb.x); y[4 * j + 3] = a[4 * j + 3] + (hi_f(w1_) + bb.y);
                }
                keep(y);
                pub = &G.r[rg].x[0][wg][c][0][wg_tid()]; tagn = 0;
                uint32_t id = (lane & 3) == lane >> 3 ? 0x3f80u << (lane & 4) * 4 : 0u;
                asm volatile("" : "+l"(pub), "+r"(tagn), "+r"(id));
                if (hl == 1) poll1(pp + 384, tag);
                load_valid(P, pp, tag);
#pragma unroll
                for (int j = 0; j < 8; j++) acc_bf(y + 4 * j, P[2 * j], P[2 * j + 1], id);
            }
#pragma unroll
            for (int j = 0; j < 16; j++) xr[j] = pack2(y[2 * j], y[2 * j + 1]);
#pragma unroll
            for (int k = 0; k < 4; k++) { raw[k] = xr[4 * k]; xr[4 * k] = tg(raw[k], tagn); }
            if (hl < 3) put_blk(pub, xr);
            if (!(hl & 1)) { release(eb, 4, l0); release(eb, 5, l0); release(eb, 6, l0); release(eb, 7, l0); }
        }
#pragma unroll
        for (int k = 0; k < 4; k++) xr[4 * k] = raw[k];
        const int ln = lane_id();
        const uint32_t ooff = (rg * 128 + (warp - 4) * 16 + (ln >> 2)) * (D_ / 8) + 8 * c + (ln & 3);
#pragma unroll
        for (int k = 0; k < 4; k++) {
            const int b = (k >> 1) * 8 + (k & 1);
            quad_t(xr[b], xr[b + 2], xr[b + 4], xr[b + 6], ln);
            reinterpret_cast<uint4*>(out)[ooff + (k >> 1) * 4 + (k & 1) * D_] = make_uint4(xr[b], xr[b + 2], xr[b + 4], xr[b + 6]);
        }
    } else {
        asm volatile("setmaxnreg.dec.sync.aligned.u32 40;");
        if (warp == 0) {
#pragma unroll 1
            for (int i = 0; i < 6; i++) {
                if (i == 4) asm volatile("bar.arrive 9, 288;" ::: "memory");
                asm volatile("{ .reg .pred p; elect.sync _|p, 0xffffffff;\n"
                             "@p mbarrier.arrive.expect_tx.shared::cta.b64 _, [%2], 16384;\n"
                             "@p cp.async.bulk.tensor.3d.shared::cluster.global.mbarrier::complete_tx::bytes.multicast::cluster [%0], [%1, {%3, %4, %5}], [%2], 3; }"
                             ::"r"(SC + SB + i * SLOT + rank * 8192), "l"(&maps.m[0]), "r"(SC + FULL + i * 8), "r"(c * 64), "r"(64 * KB(i) + 32 * rank), "r"(1) : "memory");
            }
            const int i = lane & 7, ph = lane >> 3;
            const int kb = KB(i), j = 2 * (i & 3) + rank, k = i >> 1;
            const int map = ph == 0 ? 0 : ph == 1 ? 1 + (i >> 2) : ph + 1;
            const int c0 = ph == 2 ? 0 : ph == 3 ? c ^ rank : c, c2 = ph == 0 ? 1 : ph == 2 ? 7 * c : 0;
            const int c1 = ph == 1 ? 64 * KB(j) : ph == 3 ? FS * HS(k) + 112 * (i & 1) : 64 * kb + 32 * rank;
            const uint32_t par = map | c0 << 4 | c2 << 8 | c1 << 16;
#pragma unroll 1
            for (int e = 6; e < 64; e++) {
                const uint32_t v = __shfl_sync(~0u, par, e & 31), big = e >> 4 & 1, fb = SC + FULL + (e & 7) * 8;
                mbar_wait(fb + 64, (e >> 3 & 1) ^ ((e & 7) < 6));
                asm volatile("{ .reg .pred p; elect.sync _|p, 0xffffffff;\n"
                             "@p mbarrier.arrive.expect_tx.shared::cta.b64 _, [%2], %6;\n"
                             "@p cp.async.bulk.tensor.3d.shared::cluster.global.mbarrier::complete_tx::bytes.multicast::cluster [%0], [%1, {%3, %4, %5}], [%2], 3; }"
                             ::"r"(SC + SB + (e & 7) * SLOT + rank * (big ? 14336 : 8192)), "l"(&maps.m[v & 15]), "r"(fb), "r"((v >> 4 & 15) * 64), "r"(v >> 16),
                               "r"(v >> 8 & 255), "r"(big ? SLOT : 16384) : "memory");
            }
        } else if (lane_id() >= 0 && (warp & 1)) {
            int hw = warp >> 1;
            asm volatile("" : "+r"(hw));
            if (hw == 0) {
                mbar_wait(SC + FULL, 0);
                const int w = lane >> 4, u = (lane >> 1 & 3) * 32 + 30 + (lane & 1);
                if (lane & 8) { st_ll(&G.r[rg].x[1][w][c][3][u], 0u, 0u, 0u, 0u); st_ll(&G.r[rg].o[w][c][3][u], 0u, 0u, 0u, 0u); }
                else { st_ll(&G.r[rg].h[w][c][13][u], 0u, 0u, 0u, 0u); st_ll(&G.r[rg].p[w][c ^ 1][3][u], 0u, 0u, 0u, 0u); }
                st_ll(&G.r[rg].st[1][0][0][lane][c], 0u, 0u, 0u, 0u); st_ll(&G.r[rg].st[1][1][0][lane][c], 0u, 0u, 0u, 0u);
#pragma unroll
                for (int k = 0; k < 5; k++) st_ll(&G.kvp[c][rg][min(k * 32 + lane, 143)], 0u, 0u, 0u, 0u);
                __threadfence();
                __syncwarp();
                if (lane == 0) mbar_arrive(SC + CSBAR);
                if (lane == 0) l2_prefetch(reinterpret_cast<const char*>(w2) + blockIdx.x * 14336, 14336);
            }
            if (hw) {
                mbar_wait(SC + CSBAR, 0);
#pragma unroll 1
                for (int k = 0; k < 32; k++) st_ll(&G.r[rg].x[0][k >> 4][c][0][(k & 15) * 32 + lane], 1u, 0u, 0u, 0u);
                __threadfence();
            }
            const uint4* const src = &G.kvp[c][(lane >> 3) * 4][128 + hw * 8 + (lane & 7)];
#pragma unroll 1
            for (int L = 0; L < 2; L++) {
                const uint32_t tag = 1 - L;
                uint4 v[4];
                asm volatile("bar.sync 2, 192;" ::: "memory");
#pragma unroll 1
                for (int n = 0; n < SPIN_MAX; n++) {
                    uint32_t bad = 0;
#pragma unroll
                    for (int j = 0; j < 4; j++) { v[j] = ld_ll(src + j * 144); bad |= nae(v[j].x, v[j].y, tag) | nae(v[j].z, v[j].w, tag); }
                    if (!__any_sync(~0u, bad & 1)) break;
                }
                float a0 = (uf(v[0].x) + uf(v[1].x)) + (uf(v[2].x) + uf(v[3].x)), a1 = (uf(v[0].y) + uf(v[1].y)) + (uf(v[2].y) + uf(v[3].y));
                float a2 = (uf(v[0].z) + uf(v[1].z)) + (uf(v[2].z) + uf(v[3].z)), a3 = (uf(v[0].w) + uf(v[1].w)) + (uf(v[2].w) + uf(v[3].w));
#pragma unroll
                for (int m = 8; m < 32; m <<= 1) {
                    a0 += __shfl_xor_sync(~0u, a0, m); a1 += __shfl_xor_sync(~0u, a1, m);
                    a2 += __shfl_xor_sync(~0u, a2, m); a3 += __shfl_xor_sync(~0u, a3, m);
                }
                if (lane < 8) asm volatile("st.shared.v2.u32 [%0], {%1,%2};" ::"r"(SC + P_ZF + hw * 64 + lane * 8), "r"(pack2(a0, a1)), "r"(pack2(a2, a3)) : "memory");
                __syncwarp();
                if (lane == 0) mbar_arrive(SC + KVBAR);
            if (L == 0) {
                const int l = lane_id();
                const uint4* wp = reinterpret_cast<const uint4*>(w1) + 28 * c + 4 * min(rg >> 1, 6) + ((rg & 1) * 256 + hw * 128 + (l >> 2)) * 224 + (l & 3);
                float cs[8];
#pragma unroll
                for (int j = 0; j < 8; j++) cs[j] = 0.f;
#pragma unroll 1
                for (int k = 0; k < 4; k++, wp += 4 * 8 * 224) {
                    uint4 u[4];
#pragma unroll
                    for (int j = 0; j < 4; j++) u[j] = __ldg(wp + j * 8 * 224);
#pragma unroll
                    for (int j = 0; j < 4; j++) {
                        cs[0] += lo_f(u[j].x); cs[1] += hi_f(u[j].x); cs[2] += lo_f(u[j].y); cs[3] += hi_f(u[j].y);
                        cs[4] += lo_f(u[j].z); cs[5] += hi_f(u[j].z); cs[6] += lo_f(u[j].w); cs[7] += hi_f(u[j].w);
                    }
                }
#pragma unroll
                for (int j = 0; j < 8; j++) {
#pragma unroll
                    for (int m = 4; m < 32; m <<= 1) cs[j] += __shfl_xor_sync(~0u, cs[j], m);
                }
                if (l < 4) {
#pragma unroll
                    for (int j = 0; j < 8; j += 2) sts2(SC + P_CS + hw * 128 + l * 32 + j * 4, cs[j], cs[j + 1]);
                }
                __syncwarp();
                if (l < 4) mbar_arrive(SC + CPBAR);
            }
            }
        } else {
            uint4* const mycs = &G.cs[0][c][rg * 8 + lane];
            if (lane < 8) { st_ll(mycs, 0u, 0u, 0u, 0u); st_ll(mycs + 1024, 0u, 0u, 0u, 0u); }
#pragma unroll 1
            for (int ph = 0; ph < 2; ph++) {
                mbar_wait(SC + CPBAR, ph);
                float4 a = make_float4(0.f, 0.f, 0.f, 0.f);
#pragma unroll 2
                for (int w = 0; w < 4 - 2 * ph; w++) { const float4 b = lds4(SC + P_CS + w * 128 + (lane & 7) * 16); a.x += b.x; a.y += b.y; a.z += b.z; a.w += b.w; }
                if (lane < 8) st_ll(mycs + ph * 1024, fu(a.x) | 1u, fu(a.y), fu(a.z), fu(a.w));
                __syncwarp();
                if (ph) {
                    const int ln = lane_id();
                    const uint4 vb1 = __ldg(reinterpret_cast<const uint4*>(b1) + 28 * c + min(ln, 27)), vb2 = __ldg(reinterpret_cast<const uint4*>(b2) + 8 * c + (ln & 7));
                    const uint32_t a1 = SC + SM_B1 + min(ln, 27) * 64, a2 = SC + SM_B2 + (ln & 7) * 32;
                    sts2(a1, 0.5f * lo_f(vb1.x), 0.5f * hi_f(vb1.x)); sts2(a1 + 16, 0.5f * lo_f(vb1.y), 0.5f * hi_f(vb1.y));
                    sts2(a1 + 32, 0.5f * lo_f(vb1.z), 0.5f * hi_f(vb1.z)); sts2(a1 + 48, 0.5f * lo_f(vb1.w), 0.5f * hi_f(vb1.w));
                    sts2(a2, lo_f(vb2.x), hi_f(vb2.x)); sts2(a2 + 8, lo_f(vb2.y), hi_f(vb2.y));
                    sts2(a2 + 16, lo_f(vb2.z), hi_f(vb2.z)); sts2(a2 + 24, lo_f(vb2.w), hi_f(vb2.w));
                }
                const int ln = lane_id(), k1 = min(ln + 32, 47 + 8 * ph);
                const uint4* const p0 = &G.cs[ph][c][(ln >> 3) * 16 + (ln & 7)];
                const uint4* const p1 = &G.cs[ph][c][(k1 >> 3) * 16 + (k1 & 7)];
                uint4 v[4];
#pragma unroll 1
                for (int n = 0; n < SPIN_MAX; n++) {
                    v[0] = ld_ll(p0); v[1] = ld_ll(p0 + 8); v[2] = ld_ll(p1); v[3] = ld_ll(p1 + 8);
                    if (__all_sync(~0u, v[0].x & v[1].x & v[2].x & v[3].x & 1)) break;
                }
#pragma unroll
                for (int j = 0; j < 2; j++) {
                    const int k = j ? k1 : ln;
                    const uint32_t ad = SC + (ph ? SM_B1 + 8 + k * 32 : SM_CQ + k * 16);
                    sts2(ad, uf(v[2 * j].x) + uf(v[2 * j + 1].x), uf(v[2 * j].y) + uf(v[2 * j + 1].y));
                    sts2(ad + 8 + 8 * ph, uf(v[2 * j].z) + uf(v[2 * j + 1].z), uf(v[2 * j].w) + uf(v[2 * j + 1].w));
                }
                __syncwarp();
                if (lane == 0) mbar_arrive(SC + (ph ? W1BAR : CSBAR));
            }
            mbar_wait(SC + KVBAR, 0);
            mbar_wait(SC + KVBAR, 1);
            if (lane < 8) { st_ll(mycs, 0u, 0u, 0u, 0u); st_ll(mycs + 1024, 0u, 0u, 0u, 0u); }
        }
    }
}

typedef CUresult (*EncodeFn)(CUtensorMap*, CUtensorMapDataType, cuuint32_t, void*, const cuuint64_t*, const cuuint64_t*, const cuuint32_t*,
                             const cuuint32_t*, CUtensorMapInterleave, CUtensorMapSwizzle, CUtensorMapL2promotion, CUtensorMapFloatOOBfill);

void encode(EncodeFn fn, CUtensorMap* m, const void* p, const cuuint64_t* dims, const cuuint64_t* strides, const cuuint32_t* box, CUtensorMapSwizzle sw) {
    const cuuint32_t es[3] = {1, 1, 1};
    fn(m, CU_TENSOR_MAP_DATA_TYPE_BFLOAT16, 3, const_cast<void*>(p), dims, strides, box, es, CU_TENSOR_MAP_INTERLEAVE_NONE, sw,
       CU_TENSOR_MAP_L2_PROMOTION_L2_128B, CU_TENSOR_MAP_FLOAT_OOB_FILL_NONE);
}

}

extern "C" void kernel_launch(void* const* d_in, const int* in_sizes, int n_in, void* d_out, int out_size) {
    (void)in_sizes; (void)n_in; (void)out_size;
    const __nv_bfloat16* x = (const __nv_bfloat16*)d_in[0];
    const __nv_bfloat16* wqkv = (const __nv_bfloat16*)d_in[1];
    const __nv_bfloat16* wo = (const __nv_bfloat16*)d_in[2];
    const __nv_bfloat16* w1 = (const __nv_bfloat16*)d_in[4];
    const __nv_bfloat16* b1 = (const __nv_bfloat16*)d_in[5];
    const __nv_bfloat16* w2 = (const __nv_bfloat16*)d_in[6];
    const __nv_bfloat16* b2 = (const __nv_bfloat16*)d_in[7];
    static EncodeFn fn = nullptr;
    static Xchg* gx = nullptr;
    if (!fn) {
        void* p = nullptr; cudaDriverEntryPointQueryResult q;
        cudaGetDriverEntryPoint("cuTensorMapEncodeTiled", &p, cudaEnableDefault, &q);
        fn = (EncodeFn)p;
        cudaFuncSetAttribute(fused_kernel, cudaFuncAttributeMaxDynamicSharedMemorySize, SMEM_BYTES);
        cudaGetSymbolAddress((void**)&gx, g_xchg);
    }
    Maps mp;
    { const cuuint64_t d[3] = {512, 512, 3}, s[2] = {3072, 1024}; const cuuint32_t b[3] = {64, 32, 2}; encode(fn, &mp.m[0], wqkv, d, s, b, CU_TENSOR_MAP_SWIZZLE_128B); }
    { const cuuint64_t d[3] = {512, 512, 3}, s[2] = {3072, 1024}; const cuuint32_t b[3] = {64, 64, 1}; encode(fn, &mp.m[1], wqkv, d, s, b, CU_TENSOR_MAP_SWIZZLE_128B); }
    { const cuuint64_t d[3] = {512, 512, 1}, s[2] = {1024, 524288}; const cuuint32_t b[3] = {64, 64, 1}; encode(fn, &mp.m[2], wo, d, s, b, CU_TENSOR_MAP_SWIZZLE_128B); }
    { const cuuint64_t d[3] = {32, 512, 56}, s[2] = {3584, 64}; const cuuint32_t b[3] = {32, 32, 7}; encode(fn, &mp.m[3], w1, d, s, b, CU_TENSOR_MAP_SWIZZLE_64B); }
    { const cuuint64_t d[3] = {512, 1792, 1}, s[2] = {1024, 1835008}; const cuuint32_t b[3] = {64, 112, 1}; encode(fn, &mp.m[4], w2, d, s, b, CU_TENSOR_MAP_SWIZZLE_128B); }
    { const cuuint64_t d[3] = {64, 2048, 8}, s[2] = {1024, 128}; const cuuint32_t b[3] = {64, 16, 2}; encode(fn, &mp.m[5], x, d, s, b, CU_TENSOR_MAP_SWIZZLE_128B); }
    fused_kernel<<<128, 384, SMEM_BYTES, cudaStreamPerThread>>>(gx, wqkv, wo, w1, b1, w2, b2, (__nv_bfloat16*)d_out, mp);
}
```
